```python
import torch

def _softmax(x, axis=-1):
    return torch.softmax(x, dim=axis)
def _gelu(x):
    return torch.nn.functional.gelu(x, approximate="tanh")
def _silu(x):
    return torch.nn.functional.silu(x)
def _sigmoid(x):
    return torch.sigmoid(x)
def _layernorm(x, axis=-1, eps=1e-5):
    m = x.mean(dim=axis, keepdim=True)
    v = x.var(dim=axis, keepdim=True, unbiased=False)
    return (x - m) / torch.sqrt(v + eps)
def _scatter_add(tgt, idx, src, axis=0):
    return tgt.clone().index_add_(axis, idx, src)
def _segment_sum(src, seg, n):
    out = torch.zeros((n,) + src.shape[1:], dtype=src.dtype)
    return out.index_add_(0, seg, src)
def _pad(x, pw):
    flat = tuple(v for pair in reversed(pw) for v in pair)
    return torch.nn.functional.pad(x, flat)

kernel_name = 'interleave_layers__sliding_local_dilated__ssm_conv_h3__prompt'

def setup_inputs():

    _w = (lambda a: (lambda t: t.to(torch.bfloat16) if t.is_floating_point() else t)(torch.as_tensor(a)))
    def _A_setup():
        B, S, D = 1, 2048, 512
        return {
            "x": _w((lambda *s: torch.randn(*s, dtype=torch.bfloat16) * 0.05)(B, S, D)),
            "wqkv": _w((lambda *s: torch.randn(*s, dtype=torch.bfloat16) * 0.05)(D, 3 * D)),
            "wo": _w((lambda *s: torch.randn(*s, dtype=torch.bfloat16) * 0.05)(D, D)),
        }
    _A_in = _A_setup()

    def _B_setup():
        B, S, D = 1, 2048, 512
        ks = 4
        return {
            "q": _w((lambda *s: torch.randn(*s, dtype=torch.bfloat16) * 0.05)(B, S, D)),
            "k": _w((lambda *s: torch.randn(*s, dtype=torch.bfloat16) * 0.4)(B, S, D)),
            "v": _w((lambda *s: torch.randn(*s, dtype=torch.bfloat16) * 0.4)(B, S, D)),
            "shift_k": _w((lambda *s: torch.randn(*s, dtype=torch.bfloat16) * 0.4)(D, ks) * 0.5),
            "ssm_k": _w((lambda *s: torch.randn(*s, dtype=torch.bfloat16) * 0.8)(D, S) * (1.0 / S ** 0.5)),
            "ssm_D": _w((lambda *s: torch.randn(*s, dtype=torch.bfloat16) * 0.4)(D)),
        }
    _B_in = _B_setup()

    return {
        "A_x": _A_in["x"],
        "A_wqkv": _A_in["wqkv"],
        "A_wo": _A_in["wo"],
        "B_q": _B_in["q"],
        "B_k": _B_in["k"],
        "B_v": _B_in["v"],
        "B_shift_k": _B_in["shift_k"],
        "B_ssm_k": _B_in["ssm_k"],
        "B_ssm_D": _B_in["ssm_D"],
    }

def reference(A_x, A_wqkv, A_wo, B_q, B_k, B_v, B_shift_k, B_ssm_k, B_ssm_D):
    def _A_ref(x, wqkv, wo):
        B, S, D = x.shape
        H = 32; Dh = D // H
        W, dil = 8, 2
        qkv = (lambda x, *d: x.permute(*d))((x @ wqkv).reshape(B, S, 3, H, Dh), 2, 0, 3, 1, 4)
        q, k, v = qkv[0], qkv[1], qkv[2]
        scale = Dh ** -0.5
        pos = torch.arange(S)
        off = torch.arange(W) * dil
        idx = pos[:, None] - off[None, :]
        mask = idx >= 0
        idx_c = torch.where(mask, idx, 0).reshape(-1)
        kg = k[:, :, idx_c, :].reshape(B, H, S, W, Dh)
        vg = v[:, :, idx_c, :].reshape(B, H, S, W, Dh)
        logits = torch.einsum("bhsd,bhswd->bhsw", q, kg) * scale
        logits = torch.where(mask[None, None, :, :], logits, -1e9)
        attn = _softmax(logits, axis=-1)
        o = torch.einsum("bhsw,bhswd->bhsd", attn, vg)
        return (lambda x, *d: x.permute(*d))(o, 0, 2, 1, 3).reshape(B, S, D) @ wo

    def _B_ref(q, k, v, shift_k, ssm_k, ssm_D):
        B, S, D = q.shape
        ks = shift_k.shape[-1]
        k_pad = _pad(k, ((0, 0), (ks - 1, 0), (0, 0)))
        k_shift = torch.zeros_like(k)
        for t in range(ks):
            k_shift = k_shift + k_pad[:, t:t + S, :] * shift_k[:, ks - 1 - t][None, None, :]
        kv = k_shift * v
        L = 2 * S
        kv_pad = _pad(kv, ((0, 0), (0, S), (0, 0)))
        kf_pad = _pad(ssm_k, ((0, 0), (0, S)))
        kv_f = (lambda x, axes=(-2,-1): torch.fft.rfft2(x.float(), dim=axes))(kv_pad[:, None, :, :], axes=(1, 2))
        kf_f = (lambda x, axes=(-2,-1): torch.fft.rfft2(x.float(), dim=axes))(kf_pad[:, None, :], axes=(1, 2))
        kf_f = (lambda x, *d: x.permute(*d))(kf_f, 1, 2, 0)
        y_f = kv_f * kf_f[None, :, :, :]
        y = (lambda x, s, axes=(-2,-1): torch.fft.irfft2(x, s=s, dim=axes).to(torch.bfloat16))(y_f, (1, L), axes=(1, 2))[:, 0, :S, :]
        y = y + kv * ssm_D[None, None, :]
        return q * y

    x = A_x
    x = x + _A_ref(_layernorm(x, axis=-1), A_wqkv, A_wo)
    x = x + _B_ref(_layernorm(x, axis=-1), B_k, B_v, B_shift_k, B_ssm_k, B_ssm_D)
    x = x + _A_ref(_layernorm(x, axis=-1), A_wqkv, A_wo)
    x = x + _B_ref(_layernorm(x, axis=-1), B_k, B_v, B_shift_k, B_ssm_k, B_ssm_D)
    return x
```

```cpp
#include <cuda_runtime.h>
#include <cuda_bf16.h>
#include <cuda.h>
#include <stdint.h>

namespace {

constexpr int S_LEN = 2048;
constexpr int DM = 512;
constexpr int NTHREADS = 512;
constexpr int PAUSE_KC = 4;
constexpr int HOOK_A = 23;
constexpr int W_PACE = 180;

constexpr int W_STAGE = 24576;
constexpr int X_SLOT = 17408;
constexpr int OFF_W = 0;
constexpr int OFF_WD = 98304;
constexpr int WD_SEG = 608;
constexpr int WD_DT = 16 * WD_SEG;
constexpr int WD_STRIDE = WD_DT + 128;
constexpr int OFF_X = 138240;
constexpr int OFF_U = OFF_X + 4 * X_SLOT;
constexpr int U_STRIDE = 4352;
constexpr int U_PLANE = 2176;
constexpr int OFF_ST = OFF_U + 4 * U_STRIDE;
constexpr int OFF_SK = OFF_ST + 136 * 8;
constexpr int OFF_BAR = OFF_SK + 512;
constexpr int SMEM_BYTES = OFF_BAR + 1024 + 1024;
static_assert(OFF_WD + 4 * WD_STRIDE <= OFF_X, "smem map");
static_assert(SMEM_BYTES <= 232448, "smem size");

enum {
  B_FULL = 0,
  B_EMPTY = 4,
  B_OFULL = 8,
  B_WFREE = 16,
  B_XEMPTY = 20,
  B_CONV = 24,
  B_YREAD = 28,
  B_PREP = 29,
  B_YFULL = 30,
  B_STATS = 31,
  B_ATTN = 32,
  B_X2 = 33,
  B_TAG = 34,
  B_UREADY = 35,
  B_KV = 36,
  B_RFULL = 37,
  B_RDONE = 38,
  B_STATS2 = 39,
  B_XPUB = 40,
  B_OREL = 41,
  B_YFREE = 42,
  B_COUNT = 43
};

__device__ __align__(1024) unsigned char g_o[128 * 16384];
__device__ __align__(1024) unsigned char g_x2[2 * 8 * 1032 * 128];
__device__ __align__(1024) __nv_bfloat16 g_yT[512 * 2048];
__device__ __align__(1024) __nv_bfloat16 g_uT[512 * 2048];
__device__ __align__(1024) uint2 g_st0[2 * 1032];
__device__ __align__(1024) uint2 g_stA[128 * 64];
__device__ __align__(1024) uint2 g_stB[128 * 64];
__device__ __align__(128) unsigned g_flag[128 * 32];
__device__ unsigned g_ticket;
#define TL(idx) do { } while (0)

__device__ __forceinline__ uint32_t smem_u32(const void* p) { return (uint32_t)__cvta_generic_to_shared(p); }
__device__ __forceinline__ bool elect_one() {
  uint32_t r;
  asm volatile("{.reg .pred p; elect.sync _|p, 0xffffffff; selp.u32 %0,1,0,p;}" : "=r"(r));
  return r != 0;
}
__device__ __forceinline__ void mbar_init(uint32_t bar, uint32_t cnt) {
  asm volatile("mbarrier.init.shared::cta.b64 [%0], %1;" ::"r"(bar), "r"(cnt));
}
__device__ __forceinline__ void mbar_expect_tx(uint32_t bar, uint32_t bytes) {
  asm volatile("mbarrier.arrive.expect_tx.shared::cta.b64 _, [%0], %1;" ::"r"(bar), "r"(bytes) : "memory");
}
__device__ __forceinline__ void mbar_arrive(uint32_t bar) {
  asm volatile("mbarrier.arrive.shared::cta.b64 _, [%0];" ::"r"(bar) : "memory");
}
__device__ __forceinline__ void mbar_arrive_warp(uint32_t bar) {
  __syncwarp();
  asm volatile("{.reg .pred p; elect.sync _|p, 0xffffffff; @p mbarrier.arrive.shared::cta.b64 _, [%0];}" ::"r"(bar) : "memory");
}
__device__ __forceinline__ void mbar_wait(uint32_t bar, uint32_t parity) {
  asm volatile(
      "{\n"
      ".reg .pred p;\n"
      ".reg .u32 c;\n"
      "mov.u32 c, 0;\n"
      "WAIT_L%=:\n"
      "mbarrier.try_wait.parity.shared::cta.b64 p, [%0], %1;\n"
      "@p bra WAIT_D%=;\n"
      "add.u32 c, c, 1;\n"
      "setp.lt.u32 p, c, 0x1000000;\n"
      "@p bra WAIT_L%=;\n"
      "trap;\n"
      "WAIT_D%=:\n"
      "}" ::"r"(bar), "r"(parity) : "memory");
}
__device__ __forceinline__ void bulk_load(uint32_t dst, const void* src, uint32_t bytes, uint32_t bar) {
  asm volatile("cp.async.bulk.shared::cluster.global.mbarrier::complete_tx::bytes [%0], [%1], %2, [%3];"
               ::"r"(dst), "l"(src), "r"(bytes), "r"(bar) : "memory");
}
__device__ __forceinline__ void bulk_load_mc(uint32_t dst, const void* src, uint32_t bytes, uint32_t bar) {
  asm volatile("cp.async.bulk.shared::cluster.global.mbarrier::complete_tx::bytes.multicast::cluster [%0], [%1], %2, [%3], %4;"
               ::"r"(dst), "l"(src), "r"(bytes), "r"(bar), "h"((uint16_t)3) : "memory");
}
__device__ __forceinline__ void tma_load_3d_mc(uint32_t dst, const CUtensorMap* tm, int c0, int c1, int c2, uint32_t bar) {
  asm volatile("cp.async.bulk.tensor.3d.shared::cluster.global.mbarrier::complete_tx::bytes.multicast::cluster [%0], [%1, {%3, %4, %5}], [%2], %6;"
               ::"r"(dst), "l"(tm), "r"(bar), "r"(c0), "r"(c1), "r"(c2), "h"((uint16_t)3) : "memory");
}
__device__ __forceinline__ void mbar_arrive_rank(uint32_t bar, uint32_t rank) {
  asm volatile("{.reg .b32 r; mapa.shared::cluster.u32 r, %0, %1; mbarrier.arrive.shared::cluster.b64 _, [r];}" ::"r"(bar), "r"(rank) : "memory");
}
__device__ __forceinline__ void bulk_store(void* dst, uint32_t src, uint32_t bytes) {
  asm volatile("cp.async.bulk.global.shared::cta.bulk_group [%0], [%1], %2;" ::"l"(dst), "r"(src), "r"(bytes) : "memory");
}
__device__ __forceinline__ void bulk_prefetch(const void* src, uint32_t bytes) {
  asm volatile("cp.async.bulk.prefetch.L2.global [%0], %1;" ::"l"(src), "r"(bytes) : "memory");
}
__device__ __forceinline__ void bulk_commit() { asm volatile("cp.async.bulk.commit_group;" ::: "memory"); }
__device__ __forceinline__ void bulk_wait0() { asm volatile("cp.async.bulk.wait_group 0;" ::: "memory"); }
__device__ __forceinline__ void tma_load_2d(uint32_t dst, const CUtensorMap* tm, int c0, int c1, uint32_t bar) {
  asm volatile("cp.async.bulk.tensor.2d.shared::cluster.global.mbarrier::complete_tx::bytes [%0], [%1, {%3, %4}], [%2];"
               ::"r"(dst), "l"(tm), "r"(bar), "r"(c0), "r"(c1) : "memory");
}
__device__ __forceinline__ void tma_load_3d(uint32_t dst, const CUtensorMap* tm, int c0, int c1, int c2, uint32_t bar) {
  asm volatile("cp.async.bulk.tensor.3d.shared::cluster.global.mbarrier::complete_tx::bytes [%0], [%1, {%3, %4, %5}], [%2];"
               ::"r"(dst), "l"(tm), "r"(bar), "r"(c0), "r"(c1), "r"(c2) : "memory");
}
__device__ __forceinline__ void tma_store_3d(const CUtensorMap* tm, uint32_t src, int c0, int c1, int c2) {
  asm volatile("cp.async.bulk.tensor.3d.global.shared::cta.bulk_group [%0, {%2, %3, %4}], [%1];"
               ::"l"(tm), "r"(src), "r"(c0), "r"(c1), "r"(c2) : "memory");
}
__device__ __forceinline__ void tma_store_2d(const CUtensorMap* tm, uint32_t src, int c0, int c1) {
  asm volatile("cp.async.bulk.tensor.2d.global.shared::cta.bulk_group [%0, {%2, %3}], [%1];"
               ::"l"(tm), "r"(src), "r"(c0), "r"(c1) : "memory");
}
__device__ __forceinline__ void fence_async_smem() { asm volatile("fence.proxy.async.shared::cta;" ::: "memory"); }
__device__ __forceinline__ void named_bar(int id, int n) { asm volatile("bar.sync %0, %1;" ::"r"(id), "r"(n) : "memory"); }
__device__ __forceinline__ unsigned ld_flag(const unsigned* p) {
  unsigned v;
  asm volatile("ld.acquire.gpu.global.u32 %0, [%1];" : "=r"(v) : "l"(p) : "memory");
  asm volatile("fence.proxy.async.global;" ::: "memory");
  return v;
}
__device__ __forceinline__ void st_release(unsigned* p, unsigned v) {
  asm volatile("st.release.gpu.global.u32 [%0], %1;" ::"l"(p), "r"(v) : "memory");
}
__device__ __forceinline__ void st_relaxed_v2(void* p, unsigned a, unsigned b) {
  asm volatile("{.reg .b64 t; mov.b64 t, {%1,%2}; st.relaxed.gpu.global.b64 [%0], t;}" ::"l"(p), "r"(a), "r"(b) : "memory");
}
__device__ __forceinline__ void st_relaxed_2x64(void* p, unsigned a, unsigned b, unsigned c, unsigned d) {
  asm volatile("{.reg .b64 t, u; mov.b64 t, {%1,%2}; mov.b64 u, {%3,%4}; st.relaxed.gpu.global.v2.b64 [%0], {t,u};}"
               ::"l"(p), "r"(a), "r"(b), "r"(c), "r"(d) : "memory");
}
__device__ __forceinline__ uint4 ld_relaxed_2x64(const void* p) {
  uint4 v;
  asm volatile("{.reg .b64 t, u; ld.relaxed.gpu.global.v2.b64 {t,u}, [%4]; mov.b64 {%0,%1}, t; mov.b64 {%2,%3}, u;}"
               : "=r"(v.x), "=r"(v.y), "=r"(v.z), "=r"(v.w) : "l"(p) : "memory");
  return v;
}
__device__ __forceinline__ void sts128(uint32_t a, uint32_t x, uint32_t y, uint32_t z, uint32_t w) {
  asm volatile("st.shared.v4.u32 [%0], {%1,%2,%3,%4};" ::"r"(a), "r"(x), "r"(y), "r"(z), "r"(w) : "memory");
}
__device__ __forceinline__ void sts64(uint32_t a, uint32_t x, uint32_t y) { asm volatile("st.shared.v2.u32 [%0], {%1,%2};" ::"r"(a), "r"(x), "r"(y) : "memory"); }
__device__ __forceinline__ void sts32(uint32_t a, uint32_t x) { asm volatile("st.shared.u32 [%0], %1;" ::"r"(a), "r"(x) : "memory"); }
__device__ __forceinline__ uint32_t lds32(uint32_t a) { uint32_t v; asm volatile("ld.shared.u32 %0, [%1];" : "=r"(v) : "r"(a) : "memory"); return v; }
__device__ __forceinline__ void lds128(uint32_t* r, uint32_t a) {
  asm volatile("ld.shared.v4.u32 {%0,%1,%2,%3}, [%4];" : "=r"(r[0]), "=r"(r[1]), "=r"(r[2]), "=r"(r[3]) : "r"(a) : "memory");
}
__device__ __forceinline__ void ldsm_x4(uint32_t* r, uint32_t addr) {
  asm volatile("ldmatrix.sync.aligned.m8n8.x4.shared.b16 {%0,%1,%2,%3}, [%4];"
               : "=r"(r[0]), "=r"(r[1]), "=r"(r[2]), "=r"(r[3]) : "r"(addr) : "memory");
}
__device__ __forceinline__ void ldsm_x2(uint32_t* r, uint32_t addr) {
  asm volatile("ldmatrix.sync.aligned.m8n8.x2.shared.b16 {%0,%1}, [%2];" : "=r"(r[0]), "=r"(r[1]) : "r"(addr) : "memory");
}
__device__ __forceinline__ void ldsm_x4_t(uint32_t* r, uint32_t addr) {
  asm volatile("ldmatrix.sync.aligned.m8n8.x4.trans.shared.b16 {%0,%1,%2,%3}, [%4];"
               : "=r"(r[0]), "=r"(r[1]), "=r"(r[2]), "=r"(r[3]) : "r"(addr) : "memory");
}
__device__ __forceinline__ void ldsm_x2_t(uint32_t* r, uint32_t addr) {
  asm volatile("ldmatrix.sync.aligned.m8n8.x2.trans.shared.b16 {%0,%1}, [%2];" : "=r"(r[0]), "=r"(r[1]) : "r"(addr) : "memory");
}
__device__ __forceinline__ void stsm_x4(uint32_t addr, uint32_t a, uint32_t b, uint32_t c, uint32_t d) {
  asm volatile("stmatrix.sync.aligned.m8n8.x4.shared.b16 [%0], {%1,%2,%3,%4};" ::"r"(addr), "r"(a), "r"(b), "r"(c), "r"(d) : "memory");
}
__device__ __forceinline__ void stsm_x4_t(uint32_t addr, uint32_t a, uint32_t b, uint32_t c, uint32_t d) {
  asm volatile("stmatrix.sync.aligned.m8n8.x4.trans.shared.b16 [%0], {%1,%2,%3,%4};" ::"r"(addr), "r"(a), "r"(b), "r"(c), "r"(d) : "memory");
}
__device__ __forceinline__ void stsm_x2_t(uint32_t addr, uint32_t a, uint32_t b) {
  asm volatile("stmatrix.sync.aligned.m8n8.x2.trans.shared.b16 [%0], {%1,%2};" ::"r"(addr), "r"(a), "r"(b) : "memory");
}
__device__ __forceinline__ uint32_t pack_bf16(float lo, float hi) {
  uint32_t r; asm("cvt.rn.bf16x2.f32 %0, %1, %2;" : "=r"(r) : "f"(hi), "f"(lo)); return r;
}
__device__ __forceinline__ float bf_lo(uint32_t v) { return __uint_as_float(v << 16); }
__device__ __forceinline__ float bf_hi(uint32_t v) { return __uint_as_float(v & 0xffff0000u); }
__device__ __forceinline__ uint32_t bmul2(uint32_t a, uint32_t b) { uint32_t r; asm("mul.rn.bf16x2 %0, %1, %2;" : "=r"(r) : "r"(a), "r"(b)); return r; }
__device__ __forceinline__ uint32_t badd2(uint32_t a, uint32_t b) { uint32_t r; asm("add.rn.bf16x2 %0, %1, %2;" : "=r"(r) : "r"(a), "r"(b)); return r; }
__device__ __forceinline__ uint32_t bfma2(uint32_t a, uint32_t b, uint32_t c) { uint32_t r; asm("fma.rn.bf16x2 %0, %1, %2, %3;" : "=r"(r) : "r"(a), "r"(b), "r"(c)); return r; }
__device__ __forceinline__ float rcp_fast(float x) { float r; asm("rcp.approx.ftz.f32 %0, %1;" : "=f"(r) : "f"(x)); return r; }
__device__ __forceinline__ float ex2(float x) { float r; asm("ex2.approx.ftz.f32 %0, %1;" : "=f"(r) : "f"(x)); return r; }

__device__ __forceinline__ void mma16816(float* c, uint32_t a0, uint32_t a1, uint32_t a2, uint32_t a3, uint32_t b0, uint32_t b1) {
  asm("mma.sync.aligned.m16n8k16.row.col.f32.bf16.bf16.f32 {%0,%1,%2,%3}, {%4,%5,%6,%7}, {%8,%9}, {%0,%1,%2,%3};"
      : "+f"(c[0]), "+f"(c[1]), "+f"(c[2]), "+f"(c[3]) : "r"(a0), "r"(a1), "r"(a2), "r"(a3), "r"(b0), "r"(b1));
}
__device__ __forceinline__ void mma16816z(float* c, uint32_t a0, uint32_t a1, uint32_t a2, uint32_t a3, uint32_t b0, uint32_t b1) {
  asm("mma.sync.aligned.m16n8k16.row.col.f32.bf16.bf16.f32 {%0,%1,%2,%3}, {%4,%5,%6,%7}, {%8,%9}, {%10,%10,%10,%10};"
      : "=f"(c[0]), "=f"(c[1]), "=f"(c[2]), "=f"(c[3]) : "r"(a0), "r"(a1), "r"(a2), "r"(a3), "r"(b0), "r"(b1), "f"(0.f));
}
#define OPAQUE(x) asm volatile("" : "+r"(x))
__device__ __forceinline__ void mma1688(float* c, uint32_t a0, uint32_t a1, uint32_t b0) {
  asm("mma.sync.aligned.m16n8k8.row.col.f32.bf16.bf16.f32 {%0,%1,%2,%3}, {%4,%5}, {%6}, {%0,%1,%2,%3};"
      : "+f"(c[0]), "+f"(c[1]), "+f"(c[2]), "+f"(c[3]) : "r"(a0), "r"(a1), "r"(b0));
}

#define WG_FENCE() asm volatile("wgmma.fence.sync.aligned;" ::: "memory")
#define WG_COMMIT() asm volatile("wgmma.commit_group.sync.aligned;" ::: "memory")
#define WG_WAIT(n) asm volatile("wgmma.wait_group.sync.aligned " #n ";" ::: "memory")
#define R4(i) "+f"(d[i]), "+f"(d[i + 1]), "+f"(d[i + 2]), "+f"(d[i + 3])
#define R8(i) R4(i), R4(i + 4)
__device__ __forceinline__ void wgmma_n136_ta(float* d, uint64_t da, uint64_t db, int scale_d) {
  asm volatile(
      "{.reg .pred p; setp.ne.b32 p, %70, 0;\n"
      "wgmma.mma_async.sync.aligned.m64n136k16.f32.bf16.bf16 {%0,%1,%2,%3,%4,%5,%6,%7,%8,%9,%10,%11,%12,%13,%14,%15,%16,%17,%18,%19,%20,%21,%22,%23,%24,%25,%26,%27,%28,%29,%30,%31,%32,%33,%34,%35,%36,%37,%38,%39,%40,%41,%42,%43,%44,%45,%46,%47,%48,%49,%50,%51,%52,%53,%54,%55,%56,%57,%58,%59,%60,%61,%62,%63,%64,%65,%66,%67}, %68, %69, p, 1, 1, 1, 0;}"
      : R8(0), R8(8), R8(16), R8(24), R8(32), R8(40), R8(48), R8(56), R4(64)
      : "l"(da), "l"(db), "r"(scale_d));
}
__device__ __forceinline__ void wgmma_n128_tb(float* d, uint64_t da, uint64_t db) {
  asm volatile(
      "wgmma.mma_async.sync.aligned.m64n128k16.f32.bf16.bf16 {%0,%1,%2,%3,%4,%5,%6,%7,%8,%9,%10,%11,%12,%13,%14,%15,%16,%17,%18,%19,%20,%21,%22,%23,%24,%25,%26,%27,%28,%29,%30,%31,%32,%33,%34,%35,%36,%37,%38,%39,%40,%41,%42,%43,%44,%45,%46,%47,%48,%49,%50,%51,%52,%53,%54,%55,%56,%57,%58,%59,%60,%61,%62,%63}, %64, %65, 1, 1, 1, 0, 1;"
      : R8(0), R8(8), R8(16), R8(24), R8(32), R8(40), R8(48), R8(56)
      : "l"(da), "l"(db));
}
__device__ __forceinline__ uint64_t make_desc(uint32_t addr) {
  return (uint64_t)((addr & 0x3FFFF) >> 4) | ((uint64_t)1 << 16) | ((uint64_t)64 << 32) | ((uint64_t)1 << 62);
}

__device__ __forceinline__ void chan_merge(float& m, float& q, float m2, float q2, float half_n) {
  float d = m - m2;
  q = q + q2 + d * d * half_n;
  m = 0.5f * (m + m2);
}

__device__ __forceinline__ void wgmma_n32_rs(float* d, const uint32_t* a, uint64_t db) {
  asm volatile(
      "wgmma.mma_async.sync.aligned.m64n32k16.f32.bf16.bf16 {%0,%1,%2,%3,%4,%5,%6,%7,%8,%9,%10,%11,%12,%13,%14,%15}, {%16,%17,%18,%19}, %20, 1, 1, 1, 0;"
      : R8(0), R8(8)
      : "r"(a[0]), "r"(a[1]), "r"(a[2]), "r"(a[3]), "l"(db));
}
#define W4(i) "=f"(d[i]), "=f"(d[i + 1]), "=f"(d[i + 2]), "=f"(d[i + 3])
__device__ __forceinline__ void wgmma_n32_rs_init(float* d, const uint32_t* a, uint64_t db) {
  asm volatile(
      "wgmma.mma_async.sync.aligned.m64n32k16.f32.bf16.bf16 {%0,%1,%2,%3,%4,%5,%6,%7,%8,%9,%10,%11,%12,%13,%14,%15}, {%16,%17,%18,%19}, %20, 0, 1, 1, 0;"
      : W4(0), W4(4), W4(8), W4(12)
      : "r"(a[0]), "r"(a[1]), "r"(a[2]), "r"(a[3]), "l"(db));
}
__device__ __forceinline__ void sts16(uint32_t a, uint32_t x) { asm volatile("st.shared.u16 [%0], %1;" ::"r"(a), "h"((uint16_t)x) : "memory"); }

__device__ __forceinline__ void gather_o(uint32_t sb, int b, int lane, int ly) {
  const bool el = elect_one();
  const unsigned tag = lds32(sb + OFF_BAR + 8 * B_COUNT + 8);
  const unsigned* fo = &g_flag[((b & ~7) + ((lane + (b & 6)) & 7)) * 32 + 1 + ly];
  if (lane < 8) mbar_expect_tx(sb + OFF_BAR + 8u * (B_OFULL + lane), 8192);
  unsigned pending = (b & 1) ? 0xaau : 0x55u;
  int it = 0;
  while (pending) {
    const unsigned seen = __ballot_sync(~0u, ld_flag(fo) == tag);
    unsigned ready = (seen & 3u) == 3u ? (seen & pending) : 0u;
    pending &= ~ready;
    while (ready) {
      const int c = (__ffs(ready) - 1 + (b & 6)) & 7;
      ready &= ready - 1;
      if (el) bulk_load_mc(sb + OFF_X + c * 8192, g_o + (size_t)((b & ~7) + c) * 16384 + ((b >> 2) & 1) * 8192, 8192, sb + OFF_BAR + 8u * (B_OFULL + c));
    }
    if (++it > (1 << 21)) __trap();
  }
  if (el) TL(10 + ly * 16);
}

__device__ __forceinline__ void conv_channel(uint32_t sb, int c, int wq, int lane, int bar_id, int hook_b) {
  const int gq = lane >> 2, tq = lane & 3;
  const int ao = 2 * wq + (gq & 1) - 2 * tq;
  const uint32_t wd = sb + OFF_WD + c * WD_STRIDE;
  const uint32_t wa = wd + (gq >> 1) * WD_SEG + (16 + ao) * 4;
  const uint64_t db = (uint64_t)(((sb + OFF_U + c * U_STRIDE + 128) & 0x3FFFF) >> 4) | ((uint64_t)(U_PLANE >> 4) << 16) | ((uint64_t)8 << 32);
  const uint32_t sel = 0x3210u + lds32(wd + WD_DT + 8);
  float acc[4][16];
  uint32_t a[3][4];
  {
    const uint32_t da = wd + WD_DT + (gq >= 2 ? 10 : 16 + ao) * 4;
    a[2][0] = lds32(da); a[2][1] = lds32(wd + WD_DT); a[2][2] = lds32(wd + WD_DT + 16); a[2][3] = __byte_perm(a[2][0], 0, sel);
    a[0][0] = lds32(wa); a[0][1] = lds32(wa + 32); a[0][2] = lds32(wa - 32); a[0][3] = __byte_perm(a[0][0], 0, sel);
    WG_FENCE();
#pragma unroll
    for (int q = 0; q < 4; q++) wgmma_n32_rs_init(acc[q], a[2], db + (uint64_t)(32 * q));
    WG_COMMIT();
  }
#pragma unroll
  for (int n = 0; n < 32; n++) {
    WG_WAIT(1);
    if (n < 31) {
      uint32_t* an = a[(n + 1) % 3];
      const uint32_t ad = wa + ((n + 1) >> 3) * (4 * WD_SEG) + ((n + 1) & 7) * 64;
      an[0] = lds32(ad); an[1] = lds32(ad + 32);
      an[2] = ((n + 1) & 7) ? __byte_perm(a[n % 3][1], 0, sel) : lds32(ad - 32);
      an[3] = __byte_perm(an[0], 0, sel);
    }
    WG_FENCE();
#pragma unroll
    for (int q = n >> 3; q < 4; q++) wgmma_n32_rs(acc[q], a[n % 3], db + (uint64_t)(32 * (q - (n >> 3)) - (n & 7)));
    WG_COMMIT();
    if (hook_b >= 0) {
      if (n == HOOK_A && wq == 1) {
        mbar_wait(sb + OFF_BAR + 8u * B_ATTN, 0);
        if (elect_one()) {
          TL(8);
          bulk_store(g_o + (size_t)hook_b * 16384, sb + OFF_X + 3 * X_SLOT, 16384);
          bulk_commit();
        }
        __syncwarp();
      }
    }
  }
  WG_WAIT(0);
  named_bar(bar_id, 128);
  if (hook_b >= 0 && wq == 1) {
    if (elect_one()) { bulk_wait0(); st_release(&g_flag[hook_b * 32 + 1], lds32(sb + OFF_BAR + 8 * B_COUNT + 8)); TL(9); mbar_arrive(sb + OFF_BAR + 8u * B_OREL); }
    __syncwarp();
  }
  const bool h4 = lane & 16, h3 = lane & 8;
  const uint32_t ya = wd + (gq & 1) * 2048 + (wq + (h4 ? 4 : 0)) * 2 + tq * 32 + (h3 ? 16 : 0);
  float fp0 = 0.f, fp1 = 0.f;
#pragma unroll
  for (int J = 0; J < 16; J++) {
    float f[2];
#pragma unroll
    for (int x = 0; x < 2; x++) {
      const float lo0 = acc[J >> 2][(J & 3) * 4 + x], lo1 = acc[J >> 2][(J & 3) * 4 + 2 + x];
      float hi0 = 0.f, hi1 = 0.f;
      if (J >= 2) { hi0 = acc[(J - 2) >> 2][((J - 2) & 3) * 4 + x]; hi1 = acc[(J - 2) >> 2][((J - 2) & 3) * 4 + 2 + x]; }
      f[x] = (h4 ? hi1 : lo0) + __shfl_xor_sync(~0u, h4 ? hi0 : lo1, 16);
    }
    const float o = (h3 ? fp1 : f[0]) + __shfl_xor_sync(~0u, h3 ? fp0 : f[1], 8);
    sts16(ya + J * 128, pack_bf16(o, o));
    fp0 = f[0]; fp1 = f[1];
  }
  fence_async_smem();
  mbar_arrive_warp(sb + OFF_BAR + 8u * (B_CONV + c));
}

__device__ __forceinline__ void u_chunk(uint32_t sb, int ck, int lane) {
  uint4 a;
  lds128(&a.x, sb + OFF_SK + lane * 16);
  const uint32_t w0 = __byte_perm(a.x, a.z, 0x5410), w1 = __byte_perm(a.x, a.z, 0x7632);
  const uint32_t w2 = __byte_perm(a.y, a.w, 0x5410), w3 = __byte_perm(a.y, a.w, 0x7632);
  const uint32_t ka = sb + OFF_WD + ck * 1024 + lane * 4;
  uint32_t kk[11], u[8];
#pragma unroll
  for (int i = 0; i < 11; i++) kk[i] = lds32(ka + i * 128);
#pragma unroll
  for (int i = 0; i < 8; i++) u[i] = lds32(ka + (131 + i) * 128);
#pragma unroll
  for (int i = 0; i < 8; i++) {
    uint32_t t = bmul2(kk[i], w3);
    t = badd2(t, bmul2(kk[i + 1], w2));
    t = badd2(t, bmul2(kk[i + 2], w1));
    t = badd2(t, bmul2(kk[i + 3], w0));
    u[i] = bmul2(t, u[i]);
  }
  const uint32_t tb = sb + OFF_U + (ck & 1) * 8192 + lane * 256;
  const int pos = ck >> 1;
  sts128(tb + ((pos ^ ((2 * lane) & 7)) << 4), __byte_perm(u[0], u[1], 0x5410), __byte_perm(u[2], u[3], 0x5410),
         __byte_perm(u[4], u[5], 0x5410), __byte_perm(u[6], u[7], 0x5410));
  sts128(tb + 128 + ((pos ^ ((2 * lane + 1) & 7)) << 4), __byte_perm(u[0], u[1], 0x7632), __byte_perm(u[2], u[3], 0x7632),
         __byte_perm(u[4], u[5], 0x7632), __byte_perm(u[6], u[7], 0x7632));
}

template <int NU>
__device__ __forceinline__ void attention(uint32_t sb, int rt0, int hh, int lane, bool seq_start) {
  const int gq = lane >> 2, tq = lane & 3, mat = lane >> 3, l7 = lane & 7;
  const uint32_t qa0 = sb + OFF_X + (7 + 16 * rt0 + l7 + (mat & 1) * 8) * 128 + (((2 * hh + (mat >> 1)) ^ ((l7 + 7) & 7)) << 4);
  const uint32_t ka0 = sb + OFF_X + X_SLOT + (16 * rt0 - 1 + 8 * (mat >> 1) + l7) * 128 + (((2 * hh + (mat & 1)) ^ ((l7 + 7) & 7)) << 4);
  const uint32_t va0 = qa0 + 2 * X_SLOT - 8 * 128;
  const uint32_t oa0 = sb + OFF_X + 3 * X_SLOT + (16 * rt0 + l7 + 8 * (mat & 1)) * 128 + (((2 * hh + (mat >> 1)) ^ l7) << 4);
  const bool c0 = 2 * tq > gq, c1 = 2 * tq + 1 > gq;
  const uint32_t mk = (c0 ? 0xffffu : 0u) | (c1 ? 0xffff0000u : 0u);
  const float sc = 0.25f * 1.4426950408889634f;
  const uint32_t ones = 0x3f803f80u;
  uint32_t qa[NU][4], kb[4 * NU + 2], vb[4 * NU + 2];
#pragma unroll
  for (int u = 0; u < NU; u++) { ldsm_x4(qa[u], qa0 + u * 2048); ldsm_x4(kb + 4 * u, ka0 + u * 2048); }
  ldsm_x2(kb + 4 * NU, ka0 + NU * 2048);
#pragma unroll
  for (int u = 0; u < NU; u++) ldsm_x4_t(vb + 4 * u, va0 + u * 2048);
  ldsm_x2_t(vb + 4 * NU, ka0 + X_SLOT + NU * 2048);
#pragma unroll
  for (int u = 0; u < NU; u++) {
    float s0[4], s1[4], s2[4];
    mma16816z(s0, qa[u][0], qa[u][1], qa[u][2], qa[u][3], kb[4 * u], kb[4 * u + 1]);
    mma16816z(s1, qa[u][0], qa[u][1], qa[u][2], qa[u][3], kb[4 * u + 2], kb[4 * u + 3]);
    mma16816z(s2, qa[u][0], qa[u][1], qa[u][2], qa[u][3], kb[4 * u + 4], kb[4 * u + 5]);
    if (u == 0 && seq_start) { s0[0] = -INFINITY; s0[1] = -INFINITY; }
    float lo0 = c0 ? s0[0] : s1[0], lo1 = c1 ? s0[1] : s1[1];
    float hi0 = c0 ? s1[2] : s2[2], hi1 = c1 ? s1[3] : s2[3];
    float ml = fmaxf(lo0, lo1), mh = fmaxf(hi0, hi1);
    ml = fmaxf(ml, __shfl_xor_sync(~0u, ml, 1)); mh = fmaxf(mh, __shfl_xor_sync(~0u, mh, 1));
    ml = fmaxf(ml, __shfl_xor_sync(~0u, ml, 2)); mh = fmaxf(mh, __shfl_xor_sync(~0u, mh, 2));
    ml *= -sc; mh *= -sc;
    const uint32_t plo = pack_bf16(ex2(fmaf(lo0, sc, ml)), ex2(fmaf(lo1, sc, ml)));
    const uint32_t phi = pack_bf16(ex2(fmaf(hi0, sc, mh)), ex2(fmaf(hi1, sc, mh)));
    const uint32_t a0 = plo & mk, a2 = plo & ~mk, a3 = phi & mk, a1 = phi & ~mk;
    float o0[4], o1[4], l[4] = {0.f, 0.f, 0.f, 0.f};
    mma1688(l, plo, phi, ones);
    mma16816z(o0, a0, 0u, a2, a3, vb[4 * u], vb[4 * u + 1]);
    mma16816z(o1, a0, 0u, a2, a3, vb[4 * u + 2], vb[4 * u + 3]);
    mma1688(o0, 0u, a1, vb[4 * u + 4]);
    mma1688(o1, 0u, a1, vb[4 * u + (u + 1 < NU ? 6 : 5)]);
    const float il = rcp_fast(l[0]), ih = rcp_fast(l[2]);
    stsm_x4(oa0 + u * 2048, pack_bf16(o0[0] * il, o0[1] * il), pack_bf16(o0[2] * ih, o0[3] * ih),
            pack_bf16(o1[0] * il, o1[1] * il), pack_bf16(o1[2] * ih, o1[3] * ih));
  }
}

__device__ __forceinline__ void merge_parts(const uint4& v, float* mean, float* rstd) {
  float m0 = __uint_as_float(v.x), q0 = __uint_as_float(v.y & ~0xffu), m1 = __uint_as_float(v.z), q1 = __uint_as_float(v.w & ~0xffu);
  chan_merge(m0, q0, __shfl_xor_sync(~0u, m0, 1), __shfl_xor_sync(~0u, q0, 1), 64.f);
  chan_merge(m1, q1, __shfl_xor_sync(~0u, m1, 1), __shfl_xor_sync(~0u, q1, 1), 64.f);
  chan_merge(m0, q0, __shfl_xor_sync(~0u, m0, 2), __shfl_xor_sync(~0u, q0, 2), 128.f);
  chan_merge(m1, q1, __shfl_xor_sync(~0u, m1, 2), __shfl_xor_sync(~0u, q1, 2), 128.f);
  mean[0] = m0; mean[1] = m1;
  rstd[0] = rsqrtf(q0 * (1.f / 512.f) + 1e-5f);
  rstd[1] = rsqrtf(q1 * (1.f / 512.f) + 1e-5f);
}
__device__ __forceinline__ bool tags_ok(const uint4& v, unsigned tag8) { return (((v.y ^ tag8) | (v.w ^ tag8)) & 0xffu) == 0; }
__device__ __forceinline__ unsigned with_tag(float q, unsigned tag8) { return (__float_as_uint(q) & ~0xffu) | tag8; }
__device__ __forceinline__ void tile_stats(const uint32_t* x, int lane, float& m0, float& q0, float& m1, float& q1) {
  const uint32_t ones = 0x3f803f80u;
  float s[2][4], lo[2][4], hi[2][4];
#pragma unroll
  for (int k = 0; k < 8; k++) {
    const uint32_t* a = x + 4 * k;
    if (k < 2) {
      mma16816z(s[k], a[0], a[1], a[2], a[3], ones, ones);
      mma16816z(lo[k], a[0], a[1], a[2], a[3], a[0], a[2]);
      mma16816z(hi[k], a[0], a[1], a[2], a[3], a[1], a[3]);
    } else {
      mma16816(s[k & 1], a[0], a[1], a[2], a[3], ones, ones);
      mma16816(lo[k & 1], a[0], a[1], a[2], a[3], a[0], a[2]);
      mma16816(hi[k & 1], a[0], a[1], a[2], a[3], a[1], a[3]);
    }
  }
  const bool odd = lane & 4;
  const int src = (lane & 28) | (lane >> 3);
  const float s0 = s[0][0] + s[1][0], s1 = s[0][2] + s[1][2];
  const float ss0 = __shfl_sync(~0u, odd ? lo[0][1] + lo[1][1] : lo[0][0] + lo[1][0], src);
  const float ss1 = __shfl_sync(~0u, odd ? hi[0][3] + hi[1][3] : hi[0][2] + hi[1][2], src);
  m0 = s0 * (1.f / 128.f); m1 = s1 * (1.f / 128.f);
  q0 = fmaxf(fmaf(-s0, m0, ss0), 0.f); q1 = fmaxf(fmaf(-s1, m1, ss1), 0.f);
}

struct Params {
  const __nv_bfloat16* x;
  const __nv_bfloat16* wqkv;
  const __nv_bfloat16* wo;
  const __nv_bfloat16* bk;
  const __nv_bfloat16* bv;
  const __nv_bfloat16* shift_k;
  const __nv_bfloat16* ssm_k;
  const __nv_bfloat16* ssm_D;
};

__global__ void __cluster_dims__(2, 1, 1) __launch_bounds__(NTHREADS, 1)
fused_kernel(const __grid_constant__ CUtensorMap tm_x, const __grid_constant__ CUtensorMap tm_w,
             const __grid_constant__ CUtensorMap tm_wo, const __grid_constant__ CUtensorMap tm_y,
             const __grid_constant__ CUtensorMap tm_u, const __grid_constant__ CUtensorMap tm_out,
             const __grid_constant__ CUtensorMap tm_k, const __grid_constant__ CUtensorMap tm_v,
             const __grid_constant__ CUtensorMap tm_w1, const __grid_constant__ CUtensorMap tm_xr, const Params P) {
  extern __shared__ unsigned char smem_raw[];
  const uint32_t sb = __shfl_sync(0xffffffffu, (smem_u32(smem_raw) + 1023u) & ~1023u, 0);
#define BAR(i) (sb + OFF_BAR + 8u * (uint32_t)(i))
#define S_TAG (sb + OFF_BAR + 8 * B_COUNT + 8)

  const int tid = threadIdx.x;
  const int b = blockIdx.x;
#define DERIVE_IDS() \
  const int warp = __shfl_sync(0xffffffffu, tid >> 5, 0), lane = tid & 31; \
  const int grp = b >> 3, g8 = b & 7; \
  const int par = grp & 1, rb = grp >> 1; \
  const int hf = g8 >> 2, cg = g8 & 3; \
  const int gq = lane >> 2, tq = lane & 3; \
  const int ch0 = cg * 128 + 4 * (grp * 2 + hf); \
  (void)warp; (void)lane; (void)grp; (void)g8; (void)par; (void)rb; (void)hf; (void)cg; (void)gq; (void)tq; (void)ch0;
  DERIVE_IDS();
  const uint32_t sb_ = sb; const int tid_ = tid, b_ = b;

  if (warp == 12) {
    if (elect_one()) {
      TL(0);
#pragma unroll
      for (int i = 0; i < 4; i++) {
        mbar_init(BAR(B_FULL + i), 2); mbar_init(BAR(B_EMPTY + i), 3); mbar_init(BAR(B_WFREE + i), 1);
        mbar_init(BAR(B_XEMPTY + i), 6); mbar_init(BAR(B_CONV + i), 4);
      }
#pragma unroll
      for (int i = 0; i < 8; i++) mbar_init(BAR(B_OFULL + i), 2);
      mbar_init(BAR(B_YREAD), 1);
      mbar_init(BAR(B_PREP), 12);
      mbar_init(BAR(B_YFULL), 1);
      mbar_init(BAR(B_STATS), 1);
      mbar_init(BAR(B_ATTN), 12);
      mbar_init(BAR(B_X2), 4);
      mbar_init(BAR(B_TAG), 1);
      mbar_init(BAR(B_UREADY), 4);
      mbar_init(BAR(B_KV), 1);
      mbar_init(BAR(B_RFULL), 1);
      mbar_init(BAR(B_RDONE), 4);
      mbar_init(BAR(B_STATS2), 9);
      mbar_init(BAR(B_XPUB), 1);
      mbar_init(BAR(B_OREL), 1);
      mbar_init(BAR(B_YFREE), 1);
      asm volatile("fence.mbarrier_init.release.cluster;" ::: "memory");
    }
    __syncwarp();
    asm volatile("barrier.cluster.arrive.relaxed.aligned;" ::: "memory");
    if (elect_one()) {
      mbar_expect_tx(BAR(B_FULL), W_STAGE);
      tma_load_3d(sb + OFF_W, &tm_w, g8 * 64, 0, 0, BAR(B_FULL));
    }
    __syncwarp();
    asm volatile("barrier.cluster.wait.aligned;" ::: "memory");
    if (elect_one()) {
      const int r = b & 1;
      tma_load_3d_mc(sb + OFF_X + r * X_SLOT, &tm_x, r * 64, par, rb * 128 - 7, BAR(B_FULL + r));
#pragma unroll
      for (int kc = 1; kc < 4; kc++) {
        mbar_expect_tx(BAR(B_FULL + kc), W_STAGE);
        tma_load_3d(sb + OFF_W + kc * W_STAGE, &tm_w, g8 * 64, kc * 64, 0, BAR(B_FULL + kc));
        if (kc == 2) tma_load_3d_mc(sb + OFF_X + (2 + r) * X_SLOT, &tm_x, (2 + r) * 64, par, rb * 128 - 7, BAR(B_FULL + 2 + r));
      }
      TL(1);
    }
    __syncwarp();
  } else if (warp == 13) {
    asm volatile("barrier.cluster.arrive.relaxed.aligned;" ::: "memory");
    if (elect_one()) asm volatile("prefetch.tensormap [%0];" ::"l"(&tm_x) : "memory");
    unsigned ticket = 0;
    if (lane == 0) ticket = atomicAdd(&g_ticket, 1u);
    const uint4 skw = __ldg((const uint4*)(P.shift_k + (g8 * 64 + lane * 2) * 4));
    sts128(sb + OFF_X + (lane >> 3) * X_SLOT + 135 * 128 + (lane & 7) * 16, 0x3f803f80u, 0x3f803f80u, 0x3f803f80u, 0x3f803f80u);
    fence_async_smem();
    __syncwarp();
    asm volatile("barrier.cluster.wait.aligned;" ::: "memory");
    if (lane < 4) mbar_expect_tx(BAR(B_FULL + lane), 135 * 128);
    __nanosleep(100);
    if (elect_one()) {
      bulk_prefetch(P.wqkv + 256 * 1536 + (size_t)b * 3072, 6144);
      tma_load_2d(sb + OFF_WD, &tm_k, g8 * 64, grp * 128 - 3, BAR(B_KV));
      tma_load_2d(sb + OFF_WD + 131 * 128, &tm_v, g8 * 64, grp * 128, BAR(B_KV));
    }
    sts128(sb + OFF_SK + lane * 16, skw.x, skw.y, skw.z, skw.w);
    __syncwarp();
    if (lane == 0) {
      mbar_expect_tx(BAR(B_KV), 259 * 128);
      sts32(S_TAG, (ticket >> 7) + 1u);
      mbar_arrive(BAR(B_TAG));
    }
    __syncwarp();
  } else {
    asm volatile("barrier.cluster.arrive.relaxed.aligned;" ::: "memory");
    if (tid == 32) TL(62);
    asm volatile("barrier.cluster.wait.aligned;" ::: "memory");
    if (warp == 11 && lane < 6) {
      const CUtensorMap* tmp = lane == 0 ? &tm_w1 : lane == 1 ? &tm_xr : lane == 2 ? &tm_u : lane == 3 ? &tm_wo : lane == 4 ? &tm_y : &tm_out;
      asm volatile("prefetch.tensormap [%0];" ::"l"(tmp) : "memory");
    }
  }

  float cs0 = 0.f, cs1 = 0.f;
  uint32_t xo[32];
#pragma unroll
  for (int i = 0; i < 32; i++) xo[i] = 0u;
#pragma unroll 1
  for (int layer = 0; layer < 2; layer++) {
  uint32_t sb = sb_; int tid = tid_, b = b_;
  OPAQUE(sb); OPAQUE(tid); OPAQUE(b);
  DERIVE_IDS();
  const int wg = warp >> 2, wq = warp & 3;
  const int mat = lane >> 3, l7 = lane & 7;
  const bool lead = (tid & 127) == 0;
  if (wg == 3) {
    const bool el = elect_one();
    const int rank = b & 1;
    const int aw = wq;
    if (aw == 0) {
#pragma unroll 1
      for (int kc = 4; kc < 8; kc++) {
        mbar_wait(BAR(B_EMPTY + kc - 4), 0);
        if (el) {
          mbar_expect_tx(BAR(B_FULL + kc - 4), W_STAGE);
          tma_load_3d(sb + OFF_W + (kc - 4) * W_STAGE, &tm_w, g8 * 64, kc * 64, 0, BAR(B_FULL + kc - 4));
          if (kc == 6) bulk_prefetch(P.ssm_k + (size_t)ch0 * S_LEN, 16384);
          if (kc == 7) bulk_prefetch(P.wo + (size_t)b * 2048, 4096);
        }
      }
      mbar_wait(BAR(B_TAG), 0);
      const unsigned tag8 = lds32(S_TAG) % 255u + 1u;
      const uint2* tb = &g_st0[par * 1032 + rb * 128 + lane * 2];
      uint4 v[3];
      int it = 0;
      while (true) {
        bool ok = true;
#pragma unroll
        for (int e = 0; e < 3; e++) {
          const bool act = (e < 2 || lane < 4) && !(e == 0 && lane < 4 && rb == 0);
          v[e] = make_uint4(0, 0, 0, 0);
          if (act) { v[e] = ld_relaxed_2x64(tb + e * 64); ok = ok && (((v[e].x ^ tag8) | (v[e].z ^ tag8)) & 0xffu) == 0; }
        }
        if (__all_sync(~0u, ok)) break;
        if (++it > (1 << 20)) __trap();
        __nanosleep(200);
      }
#pragma unroll
      for (int e = 0; e < 3; e++) {
        const uint32_t a = sb + OFF_ST + (e * 64 + lane * 2 - 1) * 4;
        if (e < 2 || lane < 4) {
          if (e > 0 || lane > 0) { sts32(a, v[e].x & ~0xffu); sts32(a + 544, v[e].y); }
          sts32(a + 4, v[e].z & ~0xffu); sts32(a + 548, v[e].w);
        }
      }
      if (lane < 2) sts32(sb + OFF_ST + 135 * 4 + lane * 544, 0u);
      mbar_arrive_warp(BAR(B_STATS));
      if (el) TL(52);
    } else if (aw == 1) {
#pragma unroll 1
      for (int kc = 4; kc < 8; kc++) {
        const int s = kc - 4;
        const bool mine = (kc & 1) == rank;
        mbar_wait(BAR((mine ? B_XEMPTY : B_EMPTY) + s), 0);
        if (el) {
          mbar_expect_tx(BAR(B_FULL + s), 135 * 128);
          if (mine) tma_load_3d_mc(sb + OFF_X + s * X_SLOT, &tm_x, kc * 64, par, rb * 128 - 7, BAR(B_FULL + s));
        }
      }
      const unsigned tag = lds32(S_TAG);
      mbar_wait(BAR(B_PREP), 0);
      if (el) {
        TL(48);
        tma_store_2d(&tm_u, sb + OFF_U, grp * 64, g8 * 64);
        tma_store_2d(&tm_u, sb + OFF_U + 8192, 1024 + grp * 64, g8 * 64);
        bulk_commit();
        bulk_wait0();
        st_release(&g_flag[b * 32], tag);
        TL(50);
      }
      __syncwarp();
      const unsigned* f = &g_flag[((lane & 15) * 8 + (ch0 >> 6)) * 32];
      int it = 0;
      while (!__all_sync(~0u, ld_flag(f) == tag)) { if (++it > (1 << 21)) __trap(); }
      if (el) {
        mbar_expect_tx(BAR(B_UREADY), 16384);
#pragma unroll
        for (int c = 0; c < 8; c++) bulk_load(sb + OFF_U + c * U_PLANE + 128, g_uT + (size_t)ch0 * S_LEN + c * 1024, 2048, BAR(B_UREADY));
      }
      sts128(sb + OFF_U + (lane >> 3) * U_PLANE + (lane & 7) * 16, 0, 0, 0, 0);
      sts128(sb + OFF_U + (4 + (lane >> 3)) * U_PLANE + (lane & 7) * 16, 0, 0, 0, 0);
      fence_async_smem();
      mbar_arrive_warp(BAR(B_UREADY));
    } else {
      {
        const int j0 = rb * 128 + g8 * 16 + (aw - 2) * 8;
        uint4 v[8][2];
#pragma unroll
        for (int r = 0; r < 8; r++) {
          const uint4* src = (const uint4*)(P.x + (size_t)(2 * (j0 + r) + par) * DM + lane * 16);
          v[r][0] = __ldg(src); v[r][1] = __ldg(src + 1);
        }
        float m[8], q[8];
#pragma unroll
        for (int r = 0; r < 8; r++) {
          const uint32_t w[8] = {v[r][0].x, v[r][0].y, v[r][0].z, v[r][0].w, v[r][1].x, v[r][1].y, v[r][1].z, v[r][1].w};
          float s = 0.f, ss = 0.f;
#pragma unroll
          for (int i = 0; i < 8; i++) { float a = bf_lo(w[i]), c = bf_hi(w[i]); s += a + c; ss = fmaf(a, a, fmaf(c, c, ss)); }
          m[r] = s * (1.f / 16.f);
          q[r] = fmaxf(fmaf(-s, m[r], ss), 0.f);
        }
#pragma unroll
        for (int st = 0; st < 3; st++) {
          const bool o = (lane >> st) & 1;
#pragma unroll
          for (int r = 0; r < (4 >> st); r++) {
            float mk = o ? m[2 * r + 1] : m[2 * r], qk = o ? q[2 * r + 1] : q[2 * r];
            chan_merge(mk, qk, __shfl_xor_sync(~0u, o ? m[2 * r] : m[2 * r + 1], 1 << st), __shfl_xor_sync(~0u, o ? q[2 * r] : q[2 * r + 1], 1 << st), (float)(8 << st));
            m[r] = mk; q[r] = qk;
          }
        }
        chan_merge(m[0], q[0], __shfl_xor_sync(~0u, m[0], 8), __shfl_xor_sync(~0u, q[0], 8), 64.f);
        chan_merge(m[0], q[0], __shfl_xor_sync(~0u, m[0], 16), __shfl_xor_sync(~0u, q[0], 16), 128.f);
        const float rs = __uint_as_float(__float_as_uint(rsqrtf(q[0] * (1.f / 512.f) + 1e-5f)) & ~0xffu);
        mbar_wait(BAR(B_TAG), 0);
        const unsigned tg8 = lds32(S_TAG) % 255u + 1u;
        if (lane < 8) st_relaxed_v2(&g_st0[par * 1032 + 8 + j0 + lane], __float_as_uint(rs) | tg8, __float_as_uint(-m[0]));
        if (tid == 448) TL(49);
      }
      const int cb = (aw - 2) * 2;
      uint4 hv[16];
      {
        const uint4* hsrc = (const uint4*)(P.ssm_k + (size_t)(ch0 + cb) * S_LEN) + lane;
#pragma unroll
        for (int i = 0; i < 16; i++) hv[i] = __ldg(hsrc + i * 32);
      }
      const uint32_t dv2 = *(const uint32_t*)(P.ssm_D + ch0 + cb);
      mbar_wait(BAR(B_PREP), 0);
      const uint32_t wd = sb + OFF_WD + cb * WD_STRIDE;
      if (lane < 8) sts128(wd + (lane >> 2) * WD_STRIDE + (lane & 3) * 16, 0, 0, 0, 0);
      sts32(wd + WD_DT + lane * 4, lane == 16 ? (dv2 & 0xffffu) : (lane == 17 ? dv2 << 16 : 0u));
      sts32(wd + WD_STRIDE + WD_DT + lane * 4, lane == 16 ? (dv2 >> 16) : (lane == 17 ? (dv2 & 0xffff0000u) : 0u));
      const bool sw = (lane >> 2) & 1;
      uint32_t carry = 0;
#pragma unroll
      for (int i = 0; i < 16; i++) {
        uint32_t prev = __shfl_sync(~0u, lane == 31 ? carry : hv[i].w, (lane + 31) & 31);
        carry = i == 7 ? 0u : hv[i].w;
        uint32_t a0 = __byte_perm(hv[i].x, prev, 0x7610), a1 = __byte_perm(hv[i].x, hv[i].x, 0x1032);
        uint32_t a2 = __byte_perm(hv[i].y, hv[i].x, 0x7610), a3 = __byte_perm(hv[i].y, hv[i].y, 0x1032);
        uint32_t b0 = __byte_perm(hv[i].z, hv[i].y, 0x7610), b1 = __byte_perm(hv[i].z, hv[i].z, 0x1032);
        uint32_t b2 = __byte_perm(hv[i].w, hv[i].z, 0x7610), b3 = __byte_perm(hv[i].w, hv[i].w, 0x1032);
        const uint32_t dst = wd + (i >> 3) * WD_STRIDE + (2 * (i & 7) + (lane >> 4)) * WD_SEG + 64 + (lane & 15) * 32;
        sts128(dst + (sw ? 16 : 0), sw ? b0 : a0, sw ? b1 : a1, sw ? b2 : a2, sw ? b3 : a3);
        sts128(dst + (sw ? 0 : 16), sw ? a0 : b0, sw ? a1 : b1, sw ? a2 : b2, sw ? a3 : b3);
        if ((lane & 15) >= 14 && ((i & 7) < 7 || lane < 16)) { sts128(dst + 96, a0, a1, a2, a3); sts128(dst + 112, b0, b1, b2, b3); }
      }
      if (tid == 448) TL(51);
      mbar_arrive_warp(BAR(B_UREADY));
    }
#pragma unroll
    for (int i = 0; i < 32; i++) xo[i] = 0u;
  } else {
      {
        float d[68];
        const uint32_t st_addr = sb + OFF_ST + tq * 8;
        if (layer == 1) {
          if (warp < 9) {
            const unsigned tag8 = lds32(S_TAG) % 255u + 1u;
            mbar_wait(BAR(B_XPUB), 0);
            {
              const int e = warp;
              const uint2* tb = &g_stA[(par * 64 + rb * 8 + ((e == 0 && rb == 0) ? 0 : e - 1)) * 64 + tq * 16 + gq * 2];
              uint4 v;
              int it = 0;
              while (true) {
                v = ld_relaxed_2x64(tb);
                if (__all_sync(~0u, tags_ok(v, tag8))) break;
                if (++it > (1 << 20)) __trap();
                __nanosleep(100);
              }
              float mean[2], rstd[2];
              merge_parts(v, mean, rstd);
              if (e == 0 && rb == 0) rstd[0] = rstd[1] = 0.f;
              const int i = (e - 1) * 16 + 7 + gq + (tq & 1) * 8;
              if (i >= 0) {
                const float val = (tq & 2) ? -((tq & 1) ? mean[1] : mean[0]) : ((tq & 1) ? rstd[1] : rstd[0]);
                sts32(sb + OFF_ST + i * 4 + (tq >> 1) * 544, __float_as_uint(val));
              }
            }
            mbar_arrive_warp(BAR(B_STATS2));
            if (tid == 0) TL(53);
          }
          mbar_wait(BAR(B_STATS2), 0);
        }
#pragma unroll
        for (int j = 0; j < 17; j++) {
          float n0 = 0.f, n1 = 0.f;
          asm volatile("{.reg .pred p; setp.ne.b32 p, %3, 0; @p ld.shared.v2.f32 {%0,%1}, [%2];}" : "+f"(n0), "+f"(n1) : "r"(st_addr + 544 + j * 32), "r"(layer));
          d[4 * j] = n0 * cs0; d[4 * j + 1] = n1 * cs0; d[4 * j + 2] = n0 * cs1; d[4 * j + 3] = n1 * cs1;
        }
#pragma unroll
        for (int i = 0; i < 68; i++) asm volatile("" : "+f"(d[i]) :: "memory");
        const uint64_t da0 = make_desc(sb + OFF_W + wg * 8192);
        const uint64_t db0 = make_desc(sb + OFF_X);
#pragma unroll 1
        for (int kc = 0; kc < 8; kc++) {
          const int s = kc & 3;
          const bool pause = kc == PAUSE_KC && layer == 0;
          if (pause) {
            WG_WAIT(0);
            if (lead) {
              mbar_arrive(BAR(B_EMPTY + ((kc - 1) & 3)));
              if (kc <= 4) mbar_arrive_rank(BAR(B_XEMPTY + kc - 1), (kc - 1) & 1);
            }
            mbar_wait(BAR(B_KV), 0);
            if (tid == 0) TL(20);
#pragma unroll 1
            for (int ck = warp; ck < 16; ck += 12) u_chunk(sb, ck, lane);
            fence_async_smem();
            mbar_arrive_warp(BAR(B_PREP));
            if (tid == 0) TL(27);
#pragma unroll
            for (int i = 0; i < 32; i++) xo[i] = 0u;
          }
          mbar_wait(BAR(B_FULL + s), kc >> 2);
          if (tid == 0) TL(32 + layer * 8 + kc);
          WG_FENCE();
          const uint64_t da = da0 + (uint64_t)(s * (W_STAGE >> 4)), db = db0 + (uint64_t)(s * (X_SLOT >> 4));
#pragma unroll
          for (int k = 0; k < 4; k++) wgmma_n136_ta(d, da + k * 128, db + k * 2, 1);
          WG_COMMIT();
          if (kc > 0 && !pause) {
            WG_WAIT(1);
            if (lead) {
              mbar_arrive(BAR(B_EMPTY + ((kc - 1) & 3)));
              if (kc <= 4) mbar_arrive_rank(BAR(B_XEMPTY + kc - 1), (kc - 1) & 1);
            }
          }
        }
        mbar_wait(BAR(B_STATS), 0);
        WG_WAIT(0);
#pragma unroll
        for (int i = 0; i < 68; i++) asm volatile("" : "+f"(d[i]) :: "memory");
        if (lead) mbar_arrive(BAR(B_EMPTY + 3));
        if (tid == 0) TL(6 + layer * 16);
        if (layer == 0) {
          cs0 = __shfl_sync(~0u, d[65], lane | 3);
          cs1 = __shfl_sync(~0u, d[67], lane | 3);
#pragma unroll
          for (int j = 0; j < 17; j++) {
            float n0, n1;
            asm volatile("ld.shared.v2.f32 {%0,%1}, [%2];" : "=f"(n0), "=f"(n1) : "r"(st_addr + 544 + j * 32));
            d[4 * j] = fmaf(n0, cs0, d[4 * j]); d[4 * j + 1] = fmaf(n1, cs0, d[4 * j + 1]);
            d[4 * j + 2] = fmaf(n0, cs1, d[4 * j + 2]); d[4 * j + 3] = fmaf(n1, cs1, d[4 * j + 3]);
          }
        }
        mbar_wait(BAR(B_EMPTY + wg), 1);
        if (tid == 256) TL(58 + layer);
        const uint32_t stg = sb + OFF_X + wg * X_SLOT + (8 * (mat >> 1) + l7) * 128 + (((2 * wq + (mat & 1)) ^ l7) << 4);
#pragma unroll
        for (int j = 0; j < 17; j += 2) {
          uint32_t pk[4];
#pragma unroll
          for (int e = 0; e < 2; e++) {
            if (j + e < 17) {
              float rs0, rs1;
              asm volatile("ld.shared.v2.f32 {%0,%1}, [%2];" : "=f"(rs0), "=f"(rs1) : "r"(st_addr + (j + e) * 32));
              const float* dd = d + 4 * (j + e);
              pk[2 * e] = pack_bf16(dd[0] * rs0, dd[1] * rs1);
              pk[2 * e + 1] = pack_bf16(dd[2] * rs0, dd[3] * rs1);
            }
          }
          if (j + 1 < 17) stsm_x4_t(stg + j * 1024, pk[0], pk[1], pk[2], pk[3]);
          else stsm_x2_t(stg + j * 1024, pk[0], pk[1]);
        }
      }
      named_bar(1, 384);
      if (tid == 0) TL(7 + layer * 16);
      if (wg < 2) attention<3>(sb, wg * 3, wq, lane, rb == 0 && wg == 0);
      else attention<2>(sb, 6, wq, lane, false);
      if (tid == 0) TL(60 + layer);
      fence_async_smem();
      if (layer == 1) {
        named_bar(8 + wg, 128);
        if (wq == 3 && elect_one()) {
          bulk_store(g_o + (size_t)b * 16384 + wg * 6144, sb + OFF_X + 3 * X_SLOT + wg * 6144, wg == 2 ? 4096 : 6144);
          bulk_commit();
          bulk_wait0();
        }
      }
      mbar_arrive_warp(BAR(B_ATTN));
  }
  if (layer == 0) {
    mbar_wait(BAR(B_UREADY), 0);
    if (tid == 384) TL(2);
    conv_channel(sb, wg, wq, lane, 4 + wg, wg == 3 ? b : -1);
    if (tid == 384) TL(21);
    if (tid == 0) TL(17);
    if (tid == 128) TL(18);
    if (tid == 256) TL(19);
    if (warp == 12) {
      const bool el = elect_one();
      mbar_wait(BAR(B_OREL), 0);
#pragma unroll 1
      for (int c = 0; c < 6; c++) {
        if (el) {
          mbar_expect_tx(BAR(B_OFULL + c), 16384);
          tma_load_3d(sb + OFF_W + c * 16384, &tm_wo, 0, c * 64, cg * 2, BAR(B_OFULL + c));
        }
      }
      mbar_wait(BAR(B_YFREE), 0);
      if (el) {
#pragma unroll
        for (int c = 6; c < 8; c++) {
          mbar_expect_tx(BAR(B_OFULL + c), 16384);
          tma_load_3d(sb + OFF_W + c * 16384, &tm_wo, 0, c * 64, cg * 2, BAR(B_OFULL + c));
        }
        mbar_expect_tx(BAR(B_RFULL), 16384);
        tma_load_3d(sb + OFF_U, &tm_xr, cg * 128, par, rb * 128 + hf * 64, BAR(B_RFULL));
        tma_load_3d(sb + OFF_U + 8192, &tm_xr, cg * 128 + 64, par, rb * 128 + hf * 64, BAR(B_RFULL));
      }
      __syncwarp();
    } else if (warp == 15) {
      gather_o(sb, b, lane, 0);
    } else if (warp == 14) {
      const bool el = elect_one();
#pragma unroll 1
      for (int c = 3; c >= 0; c--) {
        mbar_wait(BAR(B_CONV + c), 0);
        if (el) bulk_store(g_yT + (size_t)(ch0 + c) * S_LEN, sb + OFF_WD + c * WD_STRIDE, 4096);
      }
      if (el) {
        bulk_commit();
        bulk_wait0();
        mbar_arrive(BAR(B_YFREE));
        st_release(&g_flag[b * 32 + 3], lds32(S_TAG));
        mbar_arrive(BAR(B_YREAD));
        TL(4);
      }
      __syncwarp();
    }
#pragma unroll
    for (int i = 0; i < 32; i++) xo[i] = 0u;
  }
  if (wg == 3) {
    const bool el = elect_one();
    const int rank = b & 1;
    const int aw = wq;
    const unsigned tag = lds32(S_TAG);
    if (aw == 0) {
#pragma unroll 1
      for (int kc = 0; kc < 8; kc++) {
        const int s = kc & 3;
        if (kc >= 4) {
          mbar_wait(BAR(B_EMPTY + s), 0);
          if (el) {
            mbar_expect_tx(BAR(B_FULL + s), W_STAGE);
            tma_load_3d(sb + OFF_W + s * W_STAGE, &tm_w, g8 * 64, kc * 64, 0, BAR(B_FULL + s));
          }
        } else {
          mbar_wait(BAR(B_WFREE + s), 0);
          if (el) mbar_expect_tx(BAR(B_FULL + s), W_STAGE);
#pragma unroll 1
          for (int t = 0; t < 3; t++) {
            if (el) tma_load_3d(sb + OFF_W + s * W_STAGE + t * 8192, &tm_w1, g8 * 64, kc * 64, t, BAR(B_FULL + s));
            __nanosleep(W_PACE);
          }
        }
      }
      if (lane < 2) mbar_arrive(BAR(B_OFULL + 6 + lane));
#pragma unroll 1
      for (int c = 0; c < 6; c++) {
        mbar_wait(BAR(B_EMPTY + ((2 * c + 1) / 3)), 1);
        if (el) {
          mbar_expect_tx(BAR(B_OFULL + c), 16384);
          tma_load_3d(sb + OFF_W + c * 16384, &tm_wo, 0, c * 64, cg * 2, BAR(B_OFULL + c));
        }
      }
    } else if (aw == 1) {
#pragma unroll 1
      for (int ly = 0; ly < 2; ly++) {
        unsigned seen = 0;
        mbar_wait(BAR(B_ATTN), ly);
        if (el && ly == 1) {
          TL(8 + ly * 16);
          st_release(&g_flag[b * 32 + 1 + ly], tag);
          TL(9 + ly * 16);
        }
        __syncwarp();
        if (ly == 1) gather_o(sb, b, lane, 1);
        if (ly == 0) {
          const unsigned* f2 = (lane < 8 || lane >= 12 || rb == 0) ? &g_flag[(grp * 8 + (lane & 7)) * 32 + 4] : &g_flag[((grp - 2) * 8 + 4 + (lane - 8)) * 32 + 4];
          seen = 0;
          mbar_wait(BAR(B_X2), 0);
          if (el) {
            TL(14);
            unsigned char* dst = g_x2 + ((size_t)(par * 8 + cg * 2) * 1032 + rb * 128 + hf * 64 + 7) * 128;
            bulk_store(dst, sb + OFF_X, 8192);
            bulk_store(dst + 1032 * 128, sb + OFF_X + 8192, 8192);
            bulk_commit();
            bulk_wait0();
            st_release(&g_flag[b * 32 + 4], tag);
            mbar_arrive(BAR(B_XPUB));
            TL(15);
          }
          __syncwarp();
          int it2 = 0;
#pragma unroll 1
          for (int kc = 0; kc < 8; kc++) {
            const int s = kc & 3;
            const bool mine = (kc & 1) == rank;
            if (kc >= 4) { if (mine) mbar_wait(BAR(B_XEMPTY + s), 1); else mbar_wait(BAR(B_EMPTY + s), 0); }
            if (mine) {
              const unsigned need = (0x111u << (kc >> 1)) | (1u << (g8 ^ 1));
              while ((seen & need) != need) {
                seen = __ballot_sync(~0u, ld_flag(f2) == tag);
                if (++it2 > (1 << 21)) __trap();
              }
            }
            if (el) {
              if (kc == rank) TL(16);
              mbar_expect_tx(BAR(B_FULL + s), 135 * 128);
              if (mine) bulk_load_mc(sb + OFF_X + s * X_SLOT, g_x2 + ((size_t)(par * 8 + kc) * 1032 + rb * 128) * 128, 135 * 128, BAR(B_FULL + s));
            }
          }
        } else {
          mbar_wait(BAR(B_X2), 1);
          if (el) {
            TL(30);
            tma_store_3d(&tm_out, sb + OFF_X, cg * 128, par, rb * 128 + hf * 64);
            tma_store_3d(&tm_out, sb + OFF_X + 8192, cg * 128 + 64, par, rb * 128 + hf * 64);
            bulk_commit();
            asm volatile("cp.async.bulk.wait_group.read 0;" ::: "memory");
            TL(31);
          }
        }
      }
    } else if (aw == 3) {
      int it = 0;
      {
        const unsigned* f = &g_flag[(lane * 4 + cg) * 32 + 3];
        mbar_wait(BAR(B_YREAD), 0);
        if (el) TL(3);
        __nanosleep(100);
        while (!__all_sync(~0u, ld_flag(f) == tag)) { if (++it > (1 << 21)) __trap(); }
        mbar_wait(BAR(B_RDONE), 0);
        if (el) {
          mbar_expect_tx(BAR(B_YFULL), 16384);
          tma_load_2d(sb + OFF_U, &tm_y, par * 1024 + rb * 128 + hf * 64, cg * 128, BAR(B_YFULL));
          TL(11);
        }
      }
    }
    break;
  }
      if (wg == 2) {
        float d[64];
#pragma unroll
        for (int j = 0; j < 32; j++) { d[2 * j] = bf_lo(xo[j]); d[2 * j + 1] = bf_hi(xo[j]); }
#pragma unroll
        for (int i = 0; i < 64; i++) asm volatile("" : "+f"(d[i]) :: "memory");
        const unsigned tag8 = lds32(S_TAG) % 255u + 1u;
        const int blk = (par * 64 + rb * 8 + hf * 4 + wq) * 64;
        uint2* tb = &g_stB[blk];
        const unsigned tagB = (2u * lds32(S_TAG) + layer) % 255u + 1u;
        if (layer == 0) { mbar_wait(BAR(B_CONV), 0); mbar_wait(BAR(B_CONV + 1), 0); mbar_wait(BAR(B_CONV + 3), 0); }
        const uint64_t da0 = make_desc(sb + OFF_X);
        const uint64_t db0 = (make_desc(sb + OFF_W) & ~(uint64_t)0x3FFF0000u) | ((uint64_t)512 << 16);
#pragma unroll 1
        for (int i = 0; i < 4; i++) {
          const int c0 = (2 * i + layer * (g8 & 6)) & 7;
#pragma unroll
          for (int e = 0; e < 2; e++) {
            mbar_wait(BAR(B_OFULL + c0 + e), layer);
            if (tid == 256 && i == 0 && e == 0) TL(12 + layer * 16);
            WG_FENCE();
            const uint64_t da = da0 + (uint64_t)((c0 + e) * 512), db = db0 + (uint64_t)((c0 + e) * 1024);
#pragma unroll
            for (int k = 0; k < 4; k++) wgmma_n128_tb(d, da + k * 2, db + k * 128);
          }
          WG_COMMIT();
          WG_WAIT(1);
          if (tid == 256 && layer == 0 && i > 0) { mbar_arrive(BAR(B_WFREE + i - 1)); if (i == 3) mbar_arrive(BAR(B_WFREE + 3)); }
        }
        if (layer == 0) {
          mbar_wait(BAR(B_RFULL), 0);
          const uint32_t ra = sb + OFF_U + (wq * 16 + l7 + 8 * (mat & 1)) * 128;
#pragma unroll
          for (int j = 0; j < 16; j += 2) ldsm_x4(xo + 2 * j, ra + (j >> 3) * 8192 + ((((j & 7) + (mat >> 1)) ^ l7) << 4));
          mbar_arrive_warp(BAR(B_RDONE));
        }
        WG_WAIT(0);
        if (tid == 256) TL(13 + layer * 16);
        if (layer == 0) {
#pragma unroll
          for (int j = 0; j < 32; j++) { d[2 * j] += bf_lo(xo[j]); d[2 * j + 1] += bf_hi(xo[j]); }
        }
        float ml0, ml1;
        {
#pragma unroll
          for (int j = 0; j < 32; j++) xo[j] = pack_bf16(d[2 * j], d[2 * j + 1]);
          float q0, q1;
          tile_stats(xo, lane, ml0, q0, ml1, q1);
          if (tq == 0) st_relaxed_2x64(tb + cg * 16 + gq * 2, __float_as_uint(ml0), with_tag(q0, tagB), __float_as_uint(ml1), with_tag(q1, tagB));
        }
        if (tid == 256) TL(54 + layer);
        uint32_t xc[32];
        {
          const uint32_t nm0 = pack_bf16(-ml0, -ml0), nm1 = pack_bf16(-ml1, -ml1);
          ml0 = -bf_lo(nm0); ml1 = -bf_lo(nm1);
#pragma unroll
          for (int j = 0; j < 32; j++) xc[j] = badd2(xo[j], (j & 1) ? nm1 : nm0);
        }
#define YLOAD { const uint32_t ya = sb + OFF_U + (8 * (mat >> 1) + l7) * 128 + (((2 * wq + (mat & 1)) ^ l7) << 4); \
          _Pragma("unroll") for (int j = 0; j < 8; j++) ldsm_x4_t(yv + 4 * j, ya + j * 2048); }
        uint32_t yv[32];
#pragma unroll
        for (int j = 0; j < 32; j++) yv[j] = 0u;
        if (layer == 1) { YLOAD }
        named_bar(3, 128);
        if (layer == 0) __nanosleep(200);
        float mean[2], rstd[2];
        {
          int it = 0;
          uint4 sv = ld_relaxed_2x64(tb + tq * 16 + gq * 2), nx = ld_relaxed_2x64(tb + tq * 16 + gq * 2);
          while (!__all_sync(~0u, tags_ok(sv, tagB))) {
            sv = nx;
            nx = ld_relaxed_2x64(tb + tq * 16 + gq * 2);
            if (++it > (1 << 20)) __trap();
          }
          merge_parts(sv, mean, rstd);
        }
        if (tid == 256) TL(56 + layer);
        if (layer == 0) { mbar_wait(BAR(B_YFULL), 0); YLOAD }
        {
          const int row = wq * 16 + l7 + 8 * (mat & 1);
          const int ph = (row + (layer == 0 ? 7 : 0)) & 7;
          const uint32_t img = sb + OFF_X + row * 128;
          const float dl0 = (ml0 - mean[0]) * rstd[0], dl1 = (ml1 - mean[1]) * rstd[1];
          const uint32_t r2[2] = {pack_bf16(rstd[0], rstd[0]), pack_bf16(rstd[1], rstd[1])};
          const uint32_t o2[2] = {pack_bf16(dl0, dl0), pack_bf16(dl1, dl1)};
#pragma unroll
          for (int j = 0; j < 16; j += 2) {
#pragma unroll
            for (int e = 0; e < 4; e++) xo[2 * j + e] = bfma2(bfma2(xc[2 * j + e], r2[e & 1], o2[e & 1]), yv[2 * j + e], xo[2 * j + e]);
            stsm_x4(img + (j >> 3) * 8192 + ((((j & 7) + (mat >> 1)) ^ ph) << 4), xo[2 * j], xo[2 * j + 1], xo[2 * j + 2], xo[2 * j + 3]);
          }
          fence_async_smem();
          mbar_arrive_warp(BAR(B_X2));
          if (layer == 0) {
            float m0, q0, m1, q1;
            tile_stats(xo, lane, m0, q0, m1, q1);
            if (tq == 0) st_relaxed_2x64(&g_stA[blk + cg * 16 + gq * 2], __float_as_uint(m0), with_tag(q0, tag8), __float_as_uint(m1), with_tag(q1, tag8));
          }
        }
      }
  }
}

__device__ float f_x[S_LEN * DM], f_n[S_LEN * DM], f_o[S_LEN * DM], f_y[S_LEN * DM], f_qkv[S_LEN * 3 * DM];
__device__ __forceinline__ float rbf(float v) { return __bfloat162float(__float2bfloat16(v)); }
__global__ void fb_prep(Params P) {
  const int i = blockIdx.x * blockDim.x + threadIdx.x, s = i / DM, d = i % DM;
  f_x[i] = __bfloat162float(P.x[i]);
  float a = 0.f;
  for (int t = 0; t < 4; t++) {
    const int ss = s + t - 3;
    a = rbf(a + rbf((ss >= 0 ? __bfloat162float(P.bk[ss * DM + d]) : 0.f) * __bfloat162float(P.shift_k[d * 4 + 3 - t])));
  }
  f_n[i] = rbf(a * __bfloat162float(P.bv[i]));
}
__global__ void fb_conv(Params P) {
  const int i = blockIdx.x * blockDim.x + threadIdx.x, s = i / DM, d = i % DM;
  float a = f_n[i] * __bfloat162float(P.ssm_D[d]);
  for (int t = 0; t <= s; t++) a += f_n[(s - t) * DM + d] * __bfloat162float(P.ssm_k[d * S_LEN + t]);
  f_y[i] = rbf(a);
}
__global__ void fb_ln(int gate, __nv_bfloat16* out) {
  __shared__ float red[DM];
  const int t = threadIdx.x, i = blockIdx.x * DM + t;
  const float v = f_x[i];
  red[t] = v; __syncthreads();
  for (int s = DM / 2; s > 0; s >>= 1) { if (t < s) red[t] += red[t + s]; __syncthreads(); }
  const float m = red[0] / DM; __syncthreads();
  red[t] = (v - m) * (v - m); __syncthreads();
  for (int s = DM / 2; s > 0; s >>= 1) { if (t < s) red[t] += red[t + s]; __syncthreads(); }
  const float n = (v - m) * rsqrtf(red[0] / DM + 1e-5f);
  if (!gate) { f_n[i] = n; return; }
  const float r = rbf(v + n * f_y[i]);
  f_x[i] = r;
  if (out) out[i] = __float2bfloat16(r);
}
__global__ void fb_gemm(const __nv_bfloat16* w, int second) {
  const int N = second ? DM : 3 * DM, r = blockIdx.y, c = blockIdx.x * blockDim.x + threadIdx.x;
  const float* a = (second ? f_o : f_n) + r * DM;
  float s = 0.f;
  for (int k = 0; k < DM; k++) s += a[k] * __bfloat162float(w[k * N + c]);
  if (second) f_x[r * DM + c] += s; else f_qkv[r * N + c] = rbf(s);
}
__global__ void fb_attn() {
  const int s = blockIdx.x, h = threadIdx.x;
  float lg[8], mx = -INFINITY, sum = 0.f;
  for (int w = 0; w < 8; w++) {
    const int idx = s - 2 * w;
    float a = -INFINITY;
    if (idx >= 0) { a = 0.f; for (int d = 0; d < 16; d++) a += f_qkv[s * 1536 + h * 16 + d] * f_qkv[idx * 1536 + 512 + h * 16 + d]; a *= 0.25f; }
    lg[w] = a; mx = fmaxf(mx, a);
  }
  for (int w = 0; w < 8; w++) { lg[w] = expf(lg[w] - mx); sum += lg[w]; }
  for (int d = 0; d < 16; d++) {
    float a = 0.f;
    for (int w = 0; w < 8; w++) if (s - 2 * w >= 0) a += lg[w] * f_qkv[(s - 2 * w) * 1536 + 1024 + h * 16 + d];
    f_o[s * DM + h * 16 + d] = rbf(a / sum);
  }
}

typedef CUresult (*EncodeFn)(CUtensorMap*, CUtensorMapDataType, cuuint32_t, void*, const cuuint64_t*, const cuuint64_t*,
                             const cuuint32_t*, const cuuint32_t*, CUtensorMapInterleave, CUtensorMapSwizzle,
                             CUtensorMapL2promotion, CUtensorMapFloatOOBfill);

void encode(EncodeFn fn, CUtensorMap* tm, void* ptr, int rank, const cuuint64_t* dims, const cuuint64_t* strides, const cuuint32_t* box,
            CUtensorMapSwizzle swz = CU_TENSOR_MAP_SWIZZLE_128B) {
  cuuint32_t es[3] = {1, 1, 1};
  fn(tm, CU_TENSOR_MAP_DATA_TYPE_BFLOAT16, rank, ptr, dims, strides, box, es, CU_TENSOR_MAP_INTERLEAVE_NONE,
     swz, CU_TENSOR_MAP_L2_PROMOTION_L2_128B, CU_TENSOR_MAP_FLOAT_OOB_FILL_NONE);
}

}

extern "C" void kernel_launch(void* const* d_in, const int* in_sizes, int n_in, void* d_out, int out_size) {
  static EncodeFn fn = nullptr;
  static void* yT = nullptr;
  static void* uT = nullptr;
  static bool fused_ok = true;
  if (!fn) {
    cudaDriverEntryPointQueryResult qr;
    void* p = nullptr;
    cudaGetDriverEntryPoint("cuTensorMapEncodeTiled", &p, cudaEnableDefault, &qr);
    fn = (EncodeFn)p;
    cudaGetSymbolAddress(&yT, g_yT);
    cudaGetSymbolAddress(&uT, g_uT);
    cudaFuncSetAttribute(fused_kernel, cudaFuncAttributeMaxDynamicSharedMemorySize, SMEM_BYTES);
    cudaLaunchConfig_t cfg = {};
    cfg.gridDim = dim3(128); cfg.blockDim = dim3(NTHREADS); cfg.dynamicSmemBytes = SMEM_BYTES;
    cudaLaunchAttribute at[1];
    at[0].id = cudaLaunchAttributeClusterDimension;
    at[0].val.clusterDim.x = 2; at[0].val.clusterDim.y = 1; at[0].val.clusterDim.z = 1;
    cfg.attrs = at; cfg.numAttrs = 1;
    int ncl = 0;
    if (cudaOccupancyMaxActiveClusters(&ncl, fused_kernel, &cfg) == cudaSuccess) fused_ok = ncl >= 64;
    (void)cudaGetLastError();
  }
  CUtensorMap tm_x, tm_w, tm_wo, tm_y, tm_u, tm_out, tm_k, tm_v, tm_w1, tm_xr;
  {
    cuuint64_t dims[2] = {512, 2048}, st[1] = {1024};
    cuuint32_t boxk[2] = {64, 131}, boxv[2] = {64, 128};
    encode(fn, &tm_k, d_in[4], 2, dims, st, boxk, CU_TENSOR_MAP_SWIZZLE_NONE);
    encode(fn, &tm_v, d_in[5], 2, dims, st, boxv, CU_TENSOR_MAP_SWIZZLE_NONE);
  }
  {
    cuuint64_t dims[3] = {512, 2, 1024}, st[2] = {1024, 2048};
    cuuint32_t box[3] = {64, 1, 135};
    encode(fn, &tm_x, d_in[0], 3, dims, st, box);
    cuuint32_t boxo[3] = {64, 1, 64};
    encode(fn, &tm_out, d_out, 3, dims, st, boxo);
    encode(fn, &tm_xr, d_in[0], 3, dims, st, boxo);
  }
  {
    cuuint64_t dims[3] = {512, 512, 3}, st[2] = {3072, 1024};
    cuuint32_t box[3] = {64, 64, 3};
    encode(fn, &tm_w, d_in[1], 3, dims, st, box);
    cuuint32_t box1[3] = {64, 64, 1};
    encode(fn, &tm_w1, d_in[1], 3, dims, st, box1);
  }
  {
    cuuint64_t dims[3] = {64, 512, 8}, st[2] = {1024, 128};
    cuuint32_t box[3] = {64, 64, 2};
    encode(fn, &tm_wo, d_in[2], 3, dims, st, box);
  }
  {
    cuuint64_t dims[2] = {2048, 512}, st[1] = {4096};
    cuuint32_t box[2] = {64, 128};
    encode(fn, &tm_y, yT, 2, dims, st, box);
    cuuint32_t boxu[2] = {64, 64};
    encode(fn, &tm_u, uT, 2, dims, st, boxu);
  }
  Params P;
  P.x = (const __nv_bfloat16*)d_in[0];
  P.wqkv = (const __nv_bfloat16*)d_in[1];
  P.wo = (const __nv_bfloat16*)d_in[2];
  P.bk = (const __nv_bfloat16*)d_in[4];
  P.bv = (const __nv_bfloat16*)d_in[5];
  P.shift_k = (const __nv_bfloat16*)d_in[6];
  P.ssm_k = (const __nv_bfloat16*)d_in[7];
  P.ssm_D = (const __nv_bfloat16*)d_in[8];
  if (!fused_ok) {
    fb_prep<<<S_LEN * DM / 256, 256>>>(P);
    fb_conv<<<S_LEN * DM / 256, 256>>>(P);
    for (int l = 0; l < 2; l++) {
      fb_ln<<<S_LEN, DM>>>(0, nullptr);
      fb_gemm<<<dim3(6, S_LEN), 256>>>(P.wqkv, 0);
      fb_attn<<<S_LEN, 32>>>();
      fb_gemm<<<dim3(2, S_LEN), 256>>>(P.wo, 1);
      fb_ln<<<S_LEN, DM>>>(1, l ? (__nv_bfloat16*)d_out : nullptr);
    }
    return;
  }
  fused_kernel<<<128, NTHREADS, SMEM_BYTES>>>(tm_x, tm_w, tm_wo, tm_y, tm_u, tm_out, tm_k, tm_v, tm_w1, tm_xr, P);
}
```
